```python
import torch

def _softmax(x, axis=-1):
    return torch.softmax(x, dim=axis)
def _gelu(x):
    return torch.nn.functional.gelu(x, approximate="tanh")
def _silu(x):
    return torch.nn.functional.silu(x)
def _sigmoid(x):
    return torch.sigmoid(x)
def _layernorm(x, axis=-1, eps=1e-5):
    m = x.mean(dim=axis, keepdim=True)
    v = x.var(dim=axis, keepdim=True, unbiased=False)
    return (x - m) / torch.sqrt(v + eps)
def _scatter_add(tgt, idx, src, axis=0):
    return tgt.clone().index_add_(axis, idx, src)
def _segment_sum(src, seg, n):
    out = torch.zeros((n,) + src.shape[1:], dtype=src.dtype)
    return out.index_add_(0, seg, src)
def _pad(x, pw):
    flat = tuple(v for pair in reversed(pw) for v in pair)
    return torch.nn.functional.pad(x, flat)

kernel_name = 'sequential_preLN__compressed_kv_cla__glu_gated_geglu__decode'

def setup_inputs():

    _w = (lambda a: (lambda t: t.to(torch.bfloat16) if t.is_floating_point() else t)(torch.as_tensor(a)))
    def _A_setup():
        B, H, Sq, Sk, D, M = 1, 32, 1, 8192, 128, 640
        Dc = 4 * D
        return {
            "x": _w((lambda *s: torch.randn(*s, dtype=torch.bfloat16) * 0.05)(B, Sq, M)),
            "c_kv": _w((lambda *s: torch.randn(*s, dtype=torch.bfloat16) * 0.8)(B, Sk, Dc)),
            "w_q": _w((lambda *s: torch.randn(*s, dtype=torch.bfloat16) * 1.6)(M, H, D) * (M ** -0.5)),
            "w_uk": _w((lambda *s: torch.randn(*s, dtype=torch.bfloat16) * 1.6)(Dc, H, D) * (Dc ** -0.5)),
            "w_uv": _w((lambda *s: torch.randn(*s, dtype=torch.bfloat16) * 0.8)(Dc, H, D) * (Dc ** -0.5)),
            "w_o": _w((lambda *s: torch.randn(*s, dtype=torch.bfloat16) * 0.8)(H, D, M) * ((H * D) ** -0.5)),
        }
    _A_in = _A_setup()

    def _B_setup():
        B, S, Dm, Df = 1, 1, 640, 1728
        return {
            "x": _w((lambda *s: torch.randn(*s, dtype=torch.bfloat16) * 0.05)(B, S, Dm)),
            "w_gate": _w((lambda *s: torch.randn(*s, dtype=torch.bfloat16) * 0.4)(Dm, Df) * (Dm ** -0.5)),
            "w_up": _w((lambda *s: torch.randn(*s, dtype=torch.bfloat16) * 0.4)(Dm, Df) * (Dm ** -0.5)),
            "w_down": _w((lambda *s: torch.randn(*s, dtype=torch.bfloat16) * 0.4)(Df, Dm) * (Df ** -0.5)),
        }
    _B_in = _B_setup()

    return {
        "A_x": _A_in["x"],
        "A_c_kv": _A_in["c_kv"],
        "A_w_q": _A_in["w_q"],
        "A_w_uk": _A_in["w_uk"],
        "A_w_uv": _A_in["w_uv"],
        "A_w_o": _A_in["w_o"],
        "B_x": _B_in["x"],
        "B_w_gate": _B_in["w_gate"],
        "B_w_up": _B_in["w_up"],
        "B_w_down": _B_in["w_down"],
    }

def reference(A_x, A_c_kv, A_w_q, A_w_uk, A_w_uv, A_w_o, B_x, B_w_gate, B_w_up, B_w_down):
    def _A_ref(x, c_kv, w_q, w_uk, w_uv, w_o):
        B, Sq, M = x.shape[0], x.shape[1], x.shape[2]
        Sk = c_kv.shape[1]
        H, D = w_q.shape[1], w_q.shape[2]
        q = torch.einsum("bqm,mhd->bhqd", x, w_q)
        k = torch.einsum("bkc,chd->bhkd", c_kv, w_uk)
        v = torch.einsum("bkc,chd->bhkd", c_kv, w_uv)
        scores = torch.einsum("bhqd,bhkd->bhqk", q, k) * (D ** -0.5)
        off = Sk - Sq
        qi = torch.arange(Sq)[:, None]
        kj = torch.arange(Sk)[None, :]
        cmask = kj <= (qi + off)
        scores = torch.where(cmask[None, None], scores, -1e9)
        p = _softmax(scores, axis=-1)
        ctx = torch.einsum("bhqk,bhkd->bhqd", p, v)
        return torch.einsum("bhqd,hdm->bqm", ctx, w_o)

    def _B_ref(x, w_gate, w_up, w_down):
        g = torch.einsum("bsd,df->bsf", x, w_gate)
        u = torch.einsum("bsd,df->bsf", x, w_up)
        h = _gelu(g) * u
        return torch.einsum("bsf,fd->bsd", h, w_down)

    x = A_x
    h = x + _A_ref(_layernorm(x, axis=-1), A_c_kv, A_w_q, A_w_uk, A_w_uv, A_w_o)
    h2 = h + _B_ref(_layernorm(h, axis=-1), B_w_gate, B_w_up, B_w_down)
    return h2
```

```cpp
#include <cuda_runtime.h>
#include <cuda_bf16.h>
#include <cuda.h>
#include <stdint.h>

namespace {

constexpr int M_ = 640, H_ = 32, D_ = 128, DC_ = 512, SK_ = 8192, DF_ = 1728;
constexpr int NCTA = 128, NT = 256;
constexpr int NFFN = 108;
constexpr int NRS = 80;
constexpr int SPIN_MAX = 1 << 21;

__device__ float    g_x0[H_ * 4 * 128];
__device__ uint32_t g_x1[H_ * DC_ / 2];
__device__ uint32_t g_x2[128 * 128 * 64];
__device__ float2   g_x2s[128 * 128];
__device__ float    g_x2b[H_ * 4 * 128];
__device__ float    g_x3[NRS * 128 * 8];
__device__ float    g_x3b[M_];
__device__ float    g_x4[NRS * NFFN * 8];

constexpr int OFF_CKV = 0;
constexpr int OFF_WQ  = 65536;
constexpr int OFF_WUK = OFF_WQ + 40960;
constexpr int OFF_WUV = OFF_WUK + 32768;
constexpr int OFF_WO  = OFF_WUV + 32768;
constexpr int OFF_P   = OFF_WO + 40960;
constexpr int OFF_RED = OFF_P + 4608;
constexpr int OFF_VEC = OFF_RED + 4096;
constexpr int OFF_SM  = OFF_VEC + 2560;
constexpr int OFF_BAR = OFF_SM + 4096;
constexpr int SMEM_USED = OFF_BAR + 128;
constexpr int SMEM_ALLOC = SMEM_USED + 1024;
static_assert(OFF_WUK % 1024 == 0 && OFF_CKV % 1024 == 0, "swizzle alignment");
static_assert(SMEM_ALLOC <= 232448, "smem");

enum { BAR_WQ = 0, BAR_WUK, BAR_CKV, BAR_WUV, BAR_WO, BAR_GU, BAR_DN };

__device__ __forceinline__ uint32_t smem_u32(const void* p) { return (uint32_t)__cvta_generic_to_shared(p); }
__device__ __forceinline__ void mbar_init(uint32_t bar, uint32_t cnt) {
    asm volatile("mbarrier.init.shared::cta.b64 [%0], %1;" ::"r"(bar), "r"(cnt) : "memory");
}
__device__ __forceinline__ void mbar_expect_tx(uint32_t bar, uint32_t bytes) {
    asm volatile("mbarrier.arrive.expect_tx.shared::cta.b64 _, [%0], %1;" ::"r"(bar), "r"(bytes) : "memory");
}
__device__ __forceinline__ bool mbar_try_wait(uint32_t bar, uint32_t parity) {
    uint32_t ok;
    asm volatile(
        "{\n .reg .pred p;\n mbarrier.try_wait.parity.shared::cta.b64 p, [%1], %2;\n selp.u32 %0, 1, 0, p;\n}"
        : "=r"(ok) : "r"(bar), "r"(parity) : "memory");
    return ok != 0;
}
__device__ __forceinline__ void mbar_wait(uint32_t bar) {
    for (int i = 0; i < (1 << 24); ++i)
        if (mbar_try_wait(bar, 0)) break;
}
__device__ __forceinline__ void tma_load_2d(uint32_t dst, const CUtensorMap* tm, int c0, int c1, uint32_t bar) {
    asm volatile(
        "cp.async.bulk.tensor.2d.shared::cluster.global.mbarrier::complete_tx::bytes [%0], [%1, {%3, %4}], [%2];"
        ::"r"(dst), "l"(tm), "r"(bar), "r"(c0), "r"(c1) : "memory");
}
__device__ __forceinline__ void bulk_load(uint32_t dst, const void* src, uint32_t bytes, uint32_t bar) {
    asm volatile(
        "cp.async.bulk.shared::cluster.global.mbarrier::complete_tx::bytes [%0], [%1], %2, [%3];"
        ::"r"(dst), "l"(src), "r"(bytes), "r"(bar) : "memory");
}
__device__ __forceinline__ void fence_proxy_async() { asm volatile("fence.proxy.async.shared::cta;" ::: "memory"); }
__device__ __forceinline__ void named_bar_sync(int id, int n) { asm volatile("bar.sync %0, %1;" ::"r"(id), "r"(n) : "memory"); }

__device__ __forceinline__ uint4 ldr4(const void* p) {
    uint4 v;
    asm volatile("ld.relaxed.gpu.global.v4.u32 {%0,%1,%2,%3}, [%4];"
                 : "=r"(v.x), "=r"(v.y), "=r"(v.z), "=r"(v.w) : "l"(p) : "memory");
    return v;
}
__device__ __forceinline__ uint2 ldr2(const void* p) {
    uint2 v;
    asm volatile("ld.relaxed.gpu.global.v2.u32 {%0,%1}, [%2];" : "=r"(v.x), "=r"(v.y) : "l"(p) : "memory");
    return v;
}
__device__ __forceinline__ uint32_t ldr1(const void* p) {
    uint32_t v;
    asm volatile("ld.relaxed.gpu.global.u32 %0, [%1];" : "=r"(v) : "l"(p) : "memory");
    return v;
}
__device__ __forceinline__ void str4(void* p, uint4 v) {
    asm volatile("st.relaxed.gpu.global.v4.u32 [%0], {%1,%2,%3,%4};" ::"l"(p), "r"(v.x), "r"(v.y), "r"(v.z), "r"(v.w) : "memory");
}
__device__ __forceinline__ void str2(void* p, uint2 v) {
    asm volatile("st.relaxed.gpu.global.v2.u32 [%0], {%1,%2};" ::"l"(p), "r"(v.x), "r"(v.y) : "memory");
}
__device__ __forceinline__ void str1(void* p, uint32_t v) {
    asm volatile("st.relaxed.gpu.global.u32 [%0], %1;" ::"l"(p), "r"(v) : "memory");
}
__device__ __forceinline__ uint32_t nzw(uint32_t w) { return w ? w : 0x80000000u; }
__device__ __forceinline__ uint32_t nzf(float f) { return nzw(__float_as_uint(f)); }

__device__ __forceinline__ uint4 lds128(const void* p) { return *reinterpret_cast<const uint4*>(p); }
__device__ __forceinline__ uint2 lds64(const void* p) { return *reinterpret_cast<const uint2*>(p); }
__device__ __forceinline__ float bf_lo(uint32_t w) { return __uint_as_float(w << 16); }
__device__ __forceinline__ float bf_hi(uint32_t w) { return __uint_as_float(w & 0xffff0000u); }
__device__ __forceinline__ uint32_t pack_bf16(float lo, float hi) {
    __nv_bfloat162 v = __floats2bfloat162_rn(lo, hi);
    return *reinterpret_cast<uint32_t*>(&v);
}

__device__ __forceinline__ void ldmatrix_x4(uint32_t (&r)[4], uint32_t addr) {
    asm volatile("ldmatrix.sync.aligned.m8n8.x4.shared.b16 {%0,%1,%2,%3}, [%4];"
                 : "=r"(r[0]), "=r"(r[1]), "=r"(r[2]), "=r"(r[3]) : "r"(addr) : "memory");
}
__device__ __forceinline__ void ldmatrix_x4_trans(uint32_t (&r)[4], uint32_t addr) {
    asm volatile("ldmatrix.sync.aligned.m8n8.x4.trans.shared.b16 {%0,%1,%2,%3}, [%4];"
                 : "=r"(r[0]), "=r"(r[1]), "=r"(r[2]), "=r"(r[3]) : "r"(addr) : "memory");
}
__device__ __forceinline__ void mma_bf16(float (&d)[4], const uint32_t (&a)[4], uint32_t b0, uint32_t b1) {
    asm volatile(
        "mma.sync.aligned.m16n8k16.row.col.f32.bf16.bf16.f32 {%0,%1,%2,%3}, {%4,%5,%6,%7}, {%8,%9}, {%0,%1,%2,%3};"
        : "+f"(d[0]), "+f"(d[1]), "+f"(d[2]), "+f"(d[3])
        : "r"(a[0]), "r"(a[1]), "r"(a[2]), "r"(a[3]), "r"(b0), "r"(b1));
}

__device__ __forceinline__ uint64_t make_desc_sw128(uint32_t saddr) {
    uint64_t d = 0;
    d |= (uint64_t)((saddr & 0x3FFFF) >> 4);
    d |= (uint64_t)1 << 16;
    d |= (uint64_t)(1024 >> 4) << 32;
    d |= (uint64_t)1 << 62;
    return d;
}
__device__ __forceinline__ void wgmma_fence() { asm volatile("wgmma.fence.sync.aligned;" ::: "memory"); }
__device__ __forceinline__ void wgmma_commit() { asm volatile("wgmma.commit_group.sync.aligned;" ::: "memory"); }
__device__ __forceinline__ void wgmma_wait0() { asm volatile("wgmma.wait_group.sync.aligned 0;" ::: "memory"); }
__device__ __forceinline__ void wgmma_m64n32k16(float (&d)[16], uint64_t da, uint64_t db, int scale_d) {
    asm volatile(
        "{\n .reg .pred p;\n setp.ne.b32 p, %18, 0;\n"
        "wgmma.mma_async.sync.aligned.m64n32k16.f32.bf16.bf16 "
        "{%0,%1,%2,%3,%4,%5,%6,%7,%8,%9,%10,%11,%12,%13,%14,%15}, %16, %17, p, 1, 1, 0, 0;\n}"
        : "+f"(d[0]), "+f"(d[1]), "+f"(d[2]), "+f"(d[3]), "+f"(d[4]), "+f"(d[5]), "+f"(d[6]), "+f"(d[7]),
          "+f"(d[8]), "+f"(d[9]), "+f"(d[10]), "+f"(d[11]), "+f"(d[12]), "+f"(d[13]), "+f"(d[14]), "+f"(d[15])
        : "l"(da), "l"(db), "r"(scale_d));
}

#define TSTAMP(i) do { } while (0)

__device__ __forceinline__ float warp_sum(float v) {
#pragma unroll
    for (int o = 16; o; o >>= 1) v += __shfl_xor_sync(0xffffffffu, v, o);
    return v;
}
__device__ __forceinline__ float warp_max(float v) {
#pragma unroll
    for (int o = 16; o; o >>= 1) v = fmaxf(v, __shfl_xor_sync(0xffffffffu, v, o));
    return v;
}
__device__ __forceinline__ float block_sum(float v, float* sbuf) {
    v = warp_sum(v);
    __syncthreads();
    if ((threadIdx.x & 31) == 0) sbuf[threadIdx.x >> 5] = v;
    __syncthreads();
    float r = 0.f;
#pragma unroll
    for (int w = 0; w < 8; ++w) r += sbuf[w];
    return r;
}
__device__ __forceinline__ float block_max(float v, float* sbuf) {
    v = warp_max(v);
    __syncthreads();
    if ((threadIdx.x & 31) == 0) sbuf[threadIdx.x >> 5] = v;
    __syncthreads();
    float r = sbuf[0];
#pragma unroll
    for (int w = 1; w < 8; ++w) r = fmaxf(r, sbuf[w]);
    return r;
}

__device__ __forceinline__ void layernorm640(float* vec, float* sbuf) {
    const int t = threadIdx.x;
    float s = 0.f;
    for (int i = t; i < M_; i += NT) s += vec[i];
    const float mean = block_sum(s, sbuf) * (1.0f / M_);
    float s2 = 0.f;
    for (int i = t; i < M_; i += NT) { float d = vec[i] - mean; s2 += d * d; }
    const float var = block_sum(s2, sbuf) * (1.0f / M_);
    const float rstd = 1.0f / sqrtf(var + 1e-5f);
    for (int i = t; i < M_; i += NT) vec[i] = (vec[i] - mean) * rstd;
    __syncthreads();
}

template <int R>
__device__ __forceinline__ float vecmat128(const float* vec, const uint8_t* W, float* red) {
    const int t = threadIdx.x, lane = t & 31, warp = t >> 5;
    const int cg = t & 15, rg = t >> 4;
    float acc[8];
#pragma unroll
    for (int k = 0; k < 8; ++k) acc[k] = 0.f;
#pragma unroll
    for (int r = 0; r < R / 16; ++r) {
        const int row = rg + 16 * r;
        const uint4 w = lds128(W + row * 256 + cg * 16);
        const float v = vec[row];
        acc[0] += v * bf_lo(w.x); acc[1] += v * bf_hi(w.x);
        acc[2] += v * bf_lo(w.y); acc[3] += v * bf_hi(w.y);
        acc[4] += v * bf_lo(w.z); acc[5] += v * bf_hi(w.z);
        acc[6] += v * bf_lo(w.w); acc[7] += v * bf_hi(w.w);
    }
#pragma unroll
    for (int k = 0; k < 8; ++k) acc[k] += __shfl_xor_sync(0xffffffffu, acc[k], 16);
    __syncthreads();
    if (lane < 16) {
        float4* dst = reinterpret_cast<float4*>(red + warp * 128 + cg * 8);
        dst[0] = make_float4(acc[0], acc[1], acc[2], acc[3]);
        dst[1] = make_float4(acc[4], acc[5], acc[6], acc[7]);
    }
    __syncthreads();
    float r = 0.f;
    if (t < 128) {
#pragma unroll
        for (int w = 0; w < 8; ++w) r += red[w * 128 + t];
    }
    return r;
}

template <int R>
__device__ __forceinline__ float4 vecmat640(const float* vec, const uint8_t* W) {
    const int t = threadIdx.x;
    float4 a = make_float4(0.f, 0.f, 0.f, 0.f);
#pragma unroll 8
    for (int r = 0; r < R; ++r) {
        const uint2 w = lds64(W + r * 1280 + 8 * t);
        const float v = vec[r];
        a.x += v * bf_lo(w.x); a.y += v * bf_hi(w.x);
        a.z += v * bf_lo(w.y); a.w += v * bf_hi(w.y);
    }
    return a;
}

__device__ __forceinline__ float gelu_tanh(float g) {
    const float k0 = 0.7978845608028654f, k1 = 0.044715f;
    return 0.5f * g * (1.0f + tanhf(k0 * (g + k1 * g * g * g)));
}

__global__ void __launch_bounds__(NT, 1)
fused_decode_kernel(const __grid_constant__ CUtensorMap tm_wq, const __grid_constant__ CUtensorMap tm_wuk,
                    const __grid_constant__ CUtensorMap tm_ckv, const __grid_constant__ CUtensorMap tm_wuv,
                    const __grid_constant__ CUtensorMap tm_wg, const __grid_constant__ CUtensorMap tm_wu,
                    const __nv_bfloat16* __restrict__ x, const __nv_bfloat16* __restrict__ w_o,
                    const __nv_bfloat16* __restrict__ w_down, __nv_bfloat16* __restrict__ out) {
    extern __shared__ uint8_t smem_raw[];
    uint8_t* smem = reinterpret_cast<uint8_t*>((reinterpret_cast<uintptr_t>(smem_raw) + 1023) & ~(uintptr_t)1023);
    const int t = threadIdx.x, lane = t & 31, warp = t >> 5;
    const int b = blockIdx.x, h = b >> 2, j = b & 3;
    const uint32_t sbase = smem_u32(smem);
    const uint32_t bar0 = sbase + OFF_BAR;

    float* red   = reinterpret_cast<float*>(smem + OFF_RED);
    float* vec_s = reinterpret_cast<float*>(smem + OFF_VEC);
    float* sm    = reinterpret_cast<float*>(smem + OFF_SM);
    float* sm_q     = sm;
    float* sm_scale = sm + 128;
    float* sm_ctxc  = sm + 256;
    float* sm_ctx   = sm + 384;
    float* sm_tmp   = sm + 416;
    float* sm_wmax  = sm + 544;
    float* sm_wsum  = sm + 672;
    float* sm_act   = sm + 800;
    float* sm_red2  = sm + 816;
    float* sm_bred  = sm + 944;

    TSTAMP(0);
    if (t == 0) {
#pragma unroll
        for (int i = 0; i < 7; ++i) mbar_init(bar0 + 8 * i, 1);
        asm volatile("fence.mbarrier_init.release.cluster;" ::: "memory");
        fence_proxy_async();
    }
    __syncthreads();
    if (t == 0) {
        mbar_expect_tx(bar0 + 8 * BAR_WQ, 40960);
        tma_load_2d(sbase + OFF_WQ, &tm_wq, h * 128, 160 * j, bar0 + 8 * BAR_WQ);
        mbar_expect_tx(bar0 + 8 * BAR_WUK, 32768);
        tma_load_2d(sbase + OFF_WUK, &tm_wuk, h * 128, 128 * j, bar0 + 8 * BAR_WUK);
        mbar_expect_tx(bar0 + 8 * BAR_CKV, 65536);
#pragma unroll
        for (int kb = 0; kb < 8; ++kb)
            tma_load_2d(sbase + OFF_CKV + kb * 8192, &tm_ckv, 64 * kb, 64 * b, bar0 + 8 * BAR_CKV);
        mbar_expect_tx(bar0 + 8 * BAR_WUV, 32768);
        tma_load_2d(sbase + OFF_WUV, &tm_wuv, h * 128, 128 * j, bar0 + 8 * BAR_WUV);
        mbar_expect_tx(bar0 + 8 * BAR_WO, 40960);
        bulk_load(sbase + OFF_WO, w_o + (size_t)(h * 128 + 32 * j) * M_, 40960, bar0 + 8 * BAR_WO);
    }

    for (int i = t; i < M_; i += NT) vec_s[i] = __bfloat162float(x[i]);
    __syncthreads();
    layernorm640(vec_s, sm_bred);
    TSTAMP(1);

    mbar_wait(bar0 + 8 * BAR_WQ);
    TSTAMP(2);
    {
        const float qp = vecmat128<160>(vec_s + 160 * j, smem + OFF_WQ, red);
        if (t < 128) str1(&g_x0[(h * 4 + j) * 128 + t], nzf(qp));
    }
    if (t == 0 && b < NFFN) {
        mbar_expect_tx(bar0 + 8 * BAR_GU, 40960);
#pragma unroll
        for (int i = 0; i < 4; ++i) {
            tma_load_2d(sbase + OFF_WQ + i * 5120, &tm_wg, 16 * b, 160 * i, bar0 + 8 * BAR_GU);
            tma_load_2d(sbase + OFF_WQ + 20480 + i * 5120, &tm_wu, 16 * b, 160 * i, bar0 + 8 * BAR_GU);
        }
    }
    if (t < 128) {
        float s = 0.f;
#pragma unroll
        for (int jj = 0; jj < 4; ++jj) {
            uint32_t w = 0;
            for (int it = 0; it < SPIN_MAX; ++it) {
                w = ldr1(&g_x0[(h * 4 + jj) * 128 + t]);
                if (w) break;
            }
            s += __uint_as_float(w);
        }
        sm_q[t] = s;
    }
    __syncthreads();
    TSTAMP(3);

    mbar_wait(bar0 + 8 * BAR_WUK);
    TSTAMP(4);
    {
        const int cg = t & 15, rg = t >> 4;
        float qv[8];
#pragma unroll
        for (int k = 0; k < 8; ++k) qv[k] = sm_q[8 * cg + k];
        float acc[8];
#pragma unroll
        for (int i = 0; i < 8; ++i) {
            const int row = 32 * (i >> 1) + 2 * rg + (i & 1);
            const uint4 w = lds128(smem + OFF_WUK + row * 256 + cg * 16);
            acc[i] = qv[0] * bf_lo(w.x) + qv[1] * bf_hi(w.x) + qv[2] * bf_lo(w.y) + qv[3] * bf_hi(w.y) +
                     qv[4] * bf_lo(w.z) + qv[5] * bf_hi(w.z) + qv[6] * bf_lo(w.w) + qv[7] * bf_hi(w.w);
        }
#pragma unroll
        for (int o = 1; o <= 8; o <<= 1)
#pragma unroll
            for (int i = 0; i < 8; ++i) acc[i] += __shfl_xor_sync(0xffffffffu, acc[i], o);
        if (cg == 0) {
            const float sc = 0.08838834764831845f * 1.4426950408889634f;
#pragma unroll
            for (int k = 0; k < 4; ++k)
                str1(&g_x1[(h * DC_ + 128 * j + 32 * k + 2 * rg) >> 1],
                     nzw(pack_bf16(acc[2 * k] * sc, acc[2 * k + 1] * sc)));
        }
    }
    __syncthreads();
    TSTAMP(5);

    {
        const uint8_t* src = reinterpret_cast<const uint8_t*>(g_x1) + t * 128;
        uint4 v[8];
        for (int it = 0; it < SPIN_MAX; ++it) {
            v[0] = ldr4(src);
            if (v[0].x && v[0].y && v[0].z && v[0].w) break;
        }
#pragma unroll
        for (int i = 1; i < 8; ++i) v[i] = ldr4(src + 16 * i);
#pragma unroll
        for (int i = 1; i < 8; ++i) {
            for (int it = 0; it < SPIN_MAX; ++it) {
                if (v[i].x && v[i].y && v[i].z && v[i].w) break;
                v[i] = ldr4(src + 16 * i);
            }
        }
#pragma unroll
        for (int i = 0; i < 8; ++i) {
            const int q = 8 * t + i;
            const int hq = q >> 6, c8 = q & 63;
            *reinterpret_cast<uint4*>(smem + OFF_WUK + (c8 >> 3) * 4096 + hq * 128 + (((c8 & 7) ^ (hq & 7)) << 4)) = v[i];
        }
        fence_proxy_async();
    }
    __syncthreads();
    TSTAMP(6);

    mbar_wait(bar0 + 8 * BAR_CKV);
    TSTAMP(7);
    if (warp < 4) {
        float s[16];
#pragma unroll
        for (int i = 0; i < 16; ++i) s[i] = 0.f;
        wgmma_fence();
#pragma unroll
        for (int kb = 0; kb < 8; ++kb)
#pragma unroll
            for (int ks = 0; ks < 4; ++ks)
                wgmma_m64n32k16(s, make_desc_sw128(sbase + OFF_CKV + kb * 8192 + ks * 32),
                                make_desc_sw128(sbase + OFF_WUK + kb * 4096 + ks * 32), (kb | ks) != 0);
        wgmma_commit();
        wgmma_wait0();
        float mx[8];
#pragma unroll
        for (int i = 0; i < 4; ++i)
#pragma unroll
            for (int c = 0; c < 2; ++c) mx[2 * i + c] = fmaxf(s[4 * i + c], s[4 * i + 2 + c]);
#pragma unroll
        for (int o = 4; o <= 16; o <<= 1)
#pragma unroll
            for (int k = 0; k < 8; ++k) mx[k] = fmaxf(mx[k], __shfl_xor_sync(0xffffffffu, mx[k], o));
        if (lane < 4) {
#pragma unroll
            for (int i = 0; i < 4; ++i)
#pragma unroll
                for (int c = 0; c < 2; ++c) sm_wmax[warp * 32 + 8 * i + 2 * lane + c] = mx[2 * i + c];
        }
        named_bar_sync(1, 128);
#pragma unroll
        for (int i = 0; i < 4; ++i)
#pragma unroll
            for (int c = 0; c < 2; ++c) {
                const int head = 8 * i + 2 * (lane & 3) + c;
                mx[2 * i + c] = fmaxf(fmaxf(sm_wmax[head], sm_wmax[32 + head]), fmaxf(sm_wmax[64 + head], sm_wmax[96 + head]));
            }
        float sum[8];
#pragma unroll
        for (int i = 0; i < 4; ++i)
#pragma unroll
            for (int e = 0; e < 4; ++e) s[4 * i + e] = exp2f(s[4 * i + e] - mx[2 * i + (e & 1)]);
#pragma unroll
        for (int i = 0; i < 4; ++i)
#pragma unroll
            for (int c = 0; c < 2; ++c) sum[2 * i + c] = s[4 * i + c] + s[4 * i + 2 + c];
#pragma unroll
        for (int o = 4; o <= 16; o <<= 1)
#pragma unroll
            for (int k = 0; k < 8; ++k) sum[k] += __shfl_xor_sync(0xffffffffu, sum[k], o);
        if (lane < 4) {
#pragma unroll
            for (int i = 0; i < 4; ++i)
#pragma unroll
                for (int c = 0; c < 2; ++c) sm_wsum[warp * 32 + 8 * i + 2 * lane + c] = sum[2 * i + c];
        }
        __nv_bfloat16* Ps = reinterpret_cast<__nv_bfloat16*>(smem + OFF_P);
#pragma unroll
        for (int i = 0; i < 4; ++i)
#pragma unroll
            for (int e = 0; e < 4; ++e) {
                const int head = 8 * i + 2 * (lane & 3) + (e & 1);
                const int key = 16 * warp + (lane >> 2) + 8 * (e >> 1);
                Ps[head * 72 + key] = __float2bfloat16_rn(s[4 * i + e]);
            }
    }
    __syncthreads();
    TSTAMP(8);
    {
        uint32_t a[2][4][4];
#pragma unroll
        for (int mt = 0; mt < 2; ++mt)
#pragma unroll
            for (int ks = 0; ks < 4; ++ks)
                ldmatrix_x4(a[mt][ks], sbase + OFF_P + (16 * mt + (lane & 15)) * 144 + (16 * ks + (lane >> 4) * 8) * 2);
        float o[2][8][4];
#pragma unroll
        for (int mt = 0; mt < 2; ++mt)
#pragma unroll
            for (int nt = 0; nt < 8; ++nt)
#pragma unroll
                for (int e = 0; e < 4; ++e) o[mt][nt][e] = 0.f;
        const uint32_t blk = sbase + OFF_CKV + warp * 8192;
#pragma unroll
        for (int ks = 0; ks < 4; ++ks)
#pragma unroll
            for (int np = 0; np < 4; ++np) {
                const int m = lane >> 3;
                const int r = 16 * ks + (lane & 7) + 8 * (m & 1);
                const int ch = 2 * np + (m >> 1);
                uint32_t bf[4];
                ldmatrix_x4_trans(bf, blk + r * 128 + ((ch ^ (r & 7)) << 4));
#pragma unroll
                for (int mt = 0; mt < 2; ++mt) {
                    mma_bf16(o[mt][2 * np], a[mt][ks], bf[0], bf[1]);
                    mma_bf16(o[mt][2 * np + 1], a[mt][ks], bf[2], bf[3]);
                }
            }
        const int g = lane >> 2, tq = lane & 3;
        const int jj = warp >> 1;
#pragma unroll
        for (int mt = 0; mt < 2; ++mt)
#pragma unroll
            for (int hf = 0; hf < 2; ++hf) {
                const int head = 16 * mt + g + 8 * hf;
                uint32_t* dst = g_x2 + ((size_t)((head * 4 + jj) * 128 + b)) * 64 + (warp & 1) * 32 + tq;
#pragma unroll
                for (int nt = 0; nt < 8; ++nt)
                    str1(dst + 4 * nt, nzw(pack_bf16(o[mt][nt][2 * hf], o[mt][nt][2 * hf + 1])));
            }
    }
    if (t < 128) {
        const int head = t & 31, jj = t >> 5;
        const float m = fmaxf(fmaxf(sm_wmax[head], sm_wmax[32 + head]), fmaxf(sm_wmax[64 + head], sm_wmax[96 + head]));
        const float l = sm_wsum[head] + sm_wsum[32 + head] + sm_wsum[64 + head] + sm_wsum[96 + head];
        str2(&g_x2s[(head * 4 + jj) * 128 + b], make_uint2(nzf(m), nzf(l)));
    }
    __syncthreads();
    if (t == 0 && b < NFFN) {
        mbar_expect_tx(bar0 + 8 * BAR_DN, 20480);
        bulk_load(sbase + OFF_CKV, w_down + (size_t)(16 * b) * M_, 20480, bar0 + 8 * BAR_DN);
    }
    TSTAMP(9);

    {
        float mb = -INFINITY, lb = 0.f;
        if (t < 128) {
            uint2 w = make_uint2(0u, 0u);
            float2* p = &g_x2s[(h * 4 + j) * 128 + t];
            for (int it = 0; it < SPIN_MAX; ++it) {
                w = ldr2(p);
                if (w.x && w.y) break;
            }
            str2(p, make_uint2(0u, 0u));
            mb = __uint_as_float(w.x);
            lb = __uint_as_float(w.y);
        }
        const float Mx = block_max(mb, sm_bred);
        const float sc = (t < 128) ? exp2f(mb - Mx) : 0.f;
        const float L = block_sum(lb * sc, sm_bred);
        if (t < 128) sm_scale[t] = sc / L;
        if (t < 128) str1(&g_x0[(h * 4 + j) * 128 + t], 0u);
        else if (t < 192) str1(&g_x1[(h * DC_ + 128 * j) / 2 + (t - 128)], 0u);
        __syncthreads();
        TSTAMP(10);
        const int cg = t & 15, rg = t >> 4;
        uint32_t* base = g_x2 + (size_t)((h * 4 + j) * 128) * 64 + cg * 4;
        uint4 v[8];
#pragma unroll
        for (int i = 0; i < 8; ++i) v[i] = ldr4(base + (rg + 16 * i) * 64);
        float acc[8];
#pragma unroll
        for (int k = 0; k < 8; ++k) acc[k] = 0.f;
#pragma unroll
        for (int i = 0; i < 8; ++i) {
            for (int it = 0; it < SPIN_MAX; ++it) {
                if (v[i].x && v[i].y && v[i].z && v[i].w) break;
                v[i] = ldr4(base + (rg + 16 * i) * 64);
            }
            const float f = sm_scale[rg + 16 * i];
            acc[0] += f * bf_lo(v[i].x); acc[1] += f * bf_hi(v[i].x);
            acc[2] += f * bf_lo(v[i].y); acc[3] += f * bf_hi(v[i].y);
            acc[4] += f * bf_lo(v[i].z); acc[5] += f * bf_hi(v[i].z);
            acc[6] += f * bf_lo(v[i].w); acc[7] += f * bf_hi(v[i].w);
        }
#pragma unroll
        for (int i = 0; i < 8; ++i) str4(base + (rg + 16 * i) * 64, make_uint4(0u, 0u, 0u, 0u));
#pragma unroll
        for (int k = 0; k < 8; ++k) acc[k] += __shfl_xor_sync(0xffffffffu, acc[k], 16);
        if (lane < 16) {
            float4* dst = reinterpret_cast<float4*>(red + warp * 128 + cg * 8);
            dst[0] = make_float4(acc[0], acc[1], acc[2], acc[3]);
            dst[1] = make_float4(acc[4], acc[5], acc[6], acc[7]);
        }
        __syncthreads();
        if (t < 128) {
            float r = 0.f;
#pragma unroll
            for (int w = 0; w < 8; ++w) r += red[w * 128 + t];
            sm_ctxc[t] = r;
        }
        __syncthreads();
        TSTAMP(11);
        mbar_wait(bar0 + 8 * BAR_WUV);
        const float cp = vecmat128<128>(sm_ctxc, smem + OFF_WUV, red);
        if (t < 128) str1(&g_x2b[(h * 4 + j) * 128 + t], nzf(cp));
    }
    TSTAMP(12);

    if (t < 128) {
        const int jj = t >> 5, dd = t & 31;
        float* p = &g_x2b[(h * 4 + jj) * 128 + 32 * j + dd];
        uint32_t w = 0;
        for (int it = 0; it < SPIN_MAX; ++it) {
            w = ldr1(p);
            if (w) break;
        }
        str1(p, 0u);
        sm_tmp[t] = __uint_as_float(w);
    }
    __syncthreads();
    if (t < 32) sm_ctx[t] = (sm_tmp[t] + sm_tmp[32 + t]) + (sm_tmp[64 + t] + sm_tmp[96 + t]);
    __syncthreads();
    TSTAMP(13);
    mbar_wait(bar0 + 8 * BAR_WO);
    if (t < 160) {
        const float4 a = vecmat640<32>(sm_ctx, smem + OFF_WO);
        const int cb = t >> 1, e = (t & 1) * 4;
        str4(&g_x3[(cb * 128 + b) * 8 + e], make_uint4(nzf(a.x), nzf(a.y), nzf(a.z), nzf(a.w)));
    }
    TSTAMP(14);

    float h_own = 0.f;
    if (b < NRS) {
        float* p = &g_x3[(size_t)(b * 128) * 8 + t * 4];
        uint4 w;
        for (int it = 0; it < SPIN_MAX; ++it) {
            w = ldr4(p);
            if (w.x && w.y && w.z && w.w) break;
        }
        str4(p, make_uint4(0u, 0u, 0u, 0u));
        float v0 = __uint_as_float(w.x), v1 = __uint_as_float(w.y), v2 = __uint_as_float(w.z), v3 = __uint_as_float(w.w);
#pragma unroll
        for (int o = 2; o <= 16; o <<= 1) {
            v0 += __shfl_xor_sync(0xffffffffu, v0, o); v1 += __shfl_xor_sync(0xffffffffu, v1, o);
            v2 += __shfl_xor_sync(0xffffffffu, v2, o); v3 += __shfl_xor_sync(0xffffffffu, v3, o);
        }
        if (lane < 2) {
            float4* dst = reinterpret_cast<float4*>(sm_red2 + warp * 8 + lane * 4);
            *dst = make_float4(v0, v1, v2, v3);
        }
        __syncthreads();
        if (t < 8) {
            float a = 0.f;
#pragma unroll
            for (int w8 = 0; w8 < 8; ++w8) a += sm_red2[w8 * 8 + t];
            h_own = __bfloat162float(x[8 * b + t]) + a;
            str1(&g_x3b[8 * b + t], nzf(h_own));
        }
    }
    TSTAMP(15);

    if (b < NFFN) {
        if (t < 160) {
            const float* p = &g_x3b[4 * t];
            uint4 w;
            for (int it = 0; it < SPIN_MAX; ++it) {
                w = ldr4(p);
                if (w.x && w.y && w.z && w.w) break;
            }
            *reinterpret_cast<float4*>(vec_s + 4 * t) =
                make_float4(__uint_as_float(w.x), __uint_as_float(w.y), __uint_as_float(w.z), __uint_as_float(w.w));
        }
        __syncthreads();
        TSTAMP(16);
        layernorm640(vec_s, sm_bred);

        mbar_wait(bar0 + 8 * BAR_GU);
        TSTAMP(17);
        {
            const int mat = t >> 7, cc = t & 1, rg = (t & 127) >> 1;
            const uint8_t* W = smem + OFF_WQ + mat * 20480;
            float acc[8];
#pragma unroll
            for (int k = 0; k < 8; ++k) acc[k] = 0.f;
#pragma unroll
            for (int i = 0; i < 10; ++i) {
                const int row = rg + 64 * i;
                const uint4 w = lds128(W + row * 32 + cc * 16);
                const float v = vec_s[row];
                acc[0] += v * bf_lo(w.x); acc[1] += v * bf_hi(w.x);
                acc[2] += v * bf_lo(w.y); acc[3] += v * bf_hi(w.y);
                acc[4] += v * bf_lo(w.z); acc[5] += v * bf_hi(w.z);
                acc[6] += v * bf_lo(w.w); acc[7] += v * bf_hi(w.w);
            }
#pragma unroll
            for (int o = 2; o <= 16; o <<= 1)
#pragma unroll
                for (int k = 0; k < 8; ++k) acc[k] += __shfl_xor_sync(0xffffffffu, acc[k], o);
            if (lane < 2) {
                float4* dst = reinterpret_cast<float4*>(sm_red2 + warp * 16 + lane * 8);
                dst[0] = make_float4(acc[0], acc[1], acc[2], acc[3]);
                dst[1] = make_float4(acc[4], acc[5], acc[6], acc[7]);
            }
        }
        __syncthreads();
        if (t < 16) {
            const float gv = (sm_red2[t] + sm_red2[16 + t]) + (sm_red2[32 + t] + sm_red2[48 + t]);
            const float uv = (sm_red2[64 + t] + sm_red2[80 + t]) + (sm_red2[96 + t] + sm_red2[112 + t]);
            sm_act[t] = gelu_tanh(gv) * uv;
        }
        __syncthreads();
        mbar_wait(bar0 + 8 * BAR_DN);
        TSTAMP(18);
        if (t < 160) {
            const float4 a = vecmat640<16>(sm_act, smem + OFF_CKV);
            const int cb = t >> 1, e = (t & 1) * 4;
            str4(&g_x4[(cb * NFFN + b) * 8 + e], make_uint4(nzf(a.x), nzf(a.y), nzf(a.z), nzf(a.w)));
        }
        TSTAMP(19);
    }

    if (b < NRS) {
        float v0 = 0.f, v1 = 0.f, v2 = 0.f, v3 = 0.f;
        if (t < 2 * NFFN) {
            float* p = &g_x4[(size_t)(b * NFFN) * 8 + t * 4];
            uint4 w;
            for (int it = 0; it < SPIN_MAX; ++it) {
                w = ldr4(p);
                if (w.x && w.y && w.z && w.w) break;
            }
            str4(p, make_uint4(0u, 0u, 0u, 0u));
            v0 = __uint_as_float(w.x); v1 = __uint_as_float(w.y); v2 = __uint_as_float(w.z); v3 = __uint_as_float(w.w);
        }
#pragma unroll
        for (int o = 2; o <= 16; o <<= 1) {
            v0 += __shfl_xor_sync(0xffffffffu, v0, o); v1 += __shfl_xor_sync(0xffffffffu, v1, o);
            v2 += __shfl_xor_sync(0xffffffffu, v2, o); v3 += __shfl_xor_sync(0xffffffffu, v3, o);
        }
        __syncthreads();
        if (lane < 2) {
            float4* dst = reinterpret_cast<float4*>(sm_red2 + warp * 8 + lane * 4);
            *dst = make_float4(v0, v1, v2, v3);
        }
        __syncthreads();
        if (t < 8) {
            float a = 0.f;
#pragma unroll
            for (int w8 = 0; w8 < 8; ++w8) a += sm_red2[w8 * 8 + t];
            out[8 * b + t] = __float2bfloat16_rn(h_own + a);
            str1(&g_x3b[8 * b + t], 0u);
        }
    }
    TSTAMP(20);
}

typedef CUresult (*EncodeTiledFn)(CUtensorMap*, CUtensorMapDataType, cuuint32_t, void*, const cuuint64_t*,
                                  const cuuint64_t*, const cuuint32_t*, const cuuint32_t*, CUtensorMapInterleave,
                                  CUtensorMapSwizzle, CUtensorMapL2promotion, CUtensorMapFloatOOBfill);

bool make_map_2d(EncodeTiledFn fn, CUtensorMap* m, const void* base, uint64_t inner, uint64_t outer,
                 uint32_t box_inner, uint32_t box_outer, CUtensorMapSwizzle sw) {
    cuuint64_t gdim[2] = {inner, outer};
    cuuint64_t gstride[1] = {inner * 2};
    cuuint32_t box[2] = {box_inner, box_outer};
    cuuint32_t es[2] = {1, 1};
    return fn(m, CU_TENSOR_MAP_DATA_TYPE_BFLOAT16, 2, const_cast<void*>(base), gdim, gstride, box, es,
              CU_TENSOR_MAP_INTERLEAVE_NONE, sw, CU_TENSOR_MAP_L2_PROMOTION_L2_256B,
              CU_TENSOR_MAP_FLOAT_OOB_FILL_NONE) == CUDA_SUCCESS;
}

}

extern "C" void kernel_launch(void* const* d_in, const int* in_sizes, int n_in, void* d_out, int out_size) {
    (void)in_sizes; (void)n_in; (void)out_size;
    const __nv_bfloat16* x      = (const __nv_bfloat16*)d_in[0];
    const __nv_bfloat16* c_kv   = (const __nv_bfloat16*)d_in[1];
    const __nv_bfloat16* w_q    = (const __nv_bfloat16*)d_in[2];
    const __nv_bfloat16* w_uk   = (const __nv_bfloat16*)d_in[3];
    const __nv_bfloat16* w_uv   = (const __nv_bfloat16*)d_in[4];
    const __nv_bfloat16* w_o    = (const __nv_bfloat16*)d_in[5];
    const __nv_bfloat16* w_gate = (const __nv_bfloat16*)d_in[7];
    const __nv_bfloat16* w_up   = (const __nv_bfloat16*)d_in[8];
    const __nv_bfloat16* w_down = (const __nv_bfloat16*)d_in[9];
    __nv_bfloat16* out = (__nv_bfloat16*)d_out;

    static EncodeTiledFn fn = nullptr;
    if (!fn) {
        void* p = nullptr;
        cudaDriverEntryPointQueryResult qres;
        cudaGetDriverEntryPoint("cuTensorMapEncodeTiled", &p, cudaEnableDefault, &qres);
        fn = (EncodeTiledFn)p;
        cudaFuncSetAttribute(fused_decode_kernel, cudaFuncAttributeMaxDynamicSharedMemorySize, SMEM_ALLOC);
    }
    CUtensorMap tm_wq, tm_wuk, tm_ckv, tm_wuv, tm_wg, tm_wu;
    make_map_2d(fn, &tm_wq,  w_q,    4096, 640,  128, 160, CU_TENSOR_MAP_SWIZZLE_NONE);
    make_map_2d(fn, &tm_wuk, w_uk,   4096, 512,  128, 128, CU_TENSOR_MAP_SWIZZLE_NONE);
    make_map_2d(fn, &tm_ckv, c_kv,   512,  8192, 64,  64,  CU_TENSOR_MAP_SWIZZLE_128B);
    make_map_2d(fn, &tm_wuv, w_uv,   4096, 512,  128, 128, CU_TENSOR_MAP_SWIZZLE_NONE);
    make_map_2d(fn, &tm_wg,  w_gate, 1728, 640,  16,  160, CU_TENSOR_MAP_SWIZZLE_NONE);
    make_map_2d(fn, &tm_wu,  w_up,   1728, 640,  16,  160, CU_TENSOR_MAP_SWIZZLE_NONE);

    fused_decode_kernel<<<NCTA, NT, SMEM_ALLOC>>>(tm_wq, tm_wuk, tm_ckv, tm_wuv, tm_wg, tm_wu, x, w_o, w_down, out);
}
```

```cpp
#include <cuda_runtime.h>
#include <cuda_bf16.h>
#include <cuda.h>
#include <stdint.h>

namespace {

constexpr int M_ = 640, H_ = 32, D_ = 128, DC_ = 512, SK_ = 8192, DF_ = 1728;
constexpr int NCTA = 128, NT = 256, NTHREADS = 288;
constexpr int NFFN = 108;
constexpr int NRS = 80;
constexpr int SPIN_MAX = 1 << 21;
constexpr int X2_ROW = 288;

__device__ float    g_x0[H_ * 4 * 128];
__device__ uint32_t g_x1[H_ * DC_ / 2];
__device__ __align__(128) uint8_t g_x2[128 * 128 * X2_ROW];
__device__ float    g_x2b[H_ * 4 * 128];
__device__ float    g_x3[NRS * 128 * 8];
__device__ float    g_x3b[M_];
__device__ float    g_x4[NRS * NFFN * 8];
__device__ __align__(128) uint32_t g_cnt[4 * 32];
__device__ uint32_t g_epoch;

constexpr int OFF_CKV = 0;
constexpr int OFF_WQ  = 65536;
constexpr int OFF_WUK = OFF_WQ + 40960;
constexpr int OFF_WUV = OFF_WUK + 32768;
constexpr int OFF_WO  = OFF_WUV + 32768;
constexpr int OFF_P   = OFF_WO + 40960;
constexpr int OFF_RED = OFF_P + 4608;
constexpr int OFF_VEC = OFF_RED + 4096;
constexpr int OFF_SM  = OFF_VEC + 2560;
constexpr int OFF_BAR = OFF_SM + 4096;
constexpr int SMEM_USED = OFF_BAR + 512;
constexpr int SMEM_ALLOC = SMEM_USED + 1024;
static_assert(OFF_WUK % 1024 == 0 && OFF_CKV % 1024 == 0, "swizzle alignment");
static_assert(SMEM_ALLOC <= 232448, "smem");

enum { BAR_WQ = 0  , BAR_WUK = 4  , BAR_CKV = 8  , BAR_WUV = 16  , BAR_WO = 20  ,
       BAR_GU = 24  , BAR_DN = 32  , NPIECES = 34, BAR_FREE_WQ = 34, BAR_FREE_CKV = 35, BAR_GATE1 = 36, BAR_GATE2 = 37, NBARS = 38 };
#define INFLIGHT 4
#define GATES 1

__device__ __forceinline__ uint32_t smem_u32(const void* p) { return (uint32_t)__cvta_generic_to_shared(p); }
__device__ __forceinline__ void mbar_init(uint32_t bar, uint32_t cnt) {
    asm volatile("mbarrier.init.shared::cta.b64 [%0], %1;" ::"r"(bar), "r"(cnt) : "memory");
}
__device__ __forceinline__ void mbar_expect_tx(uint32_t bar, uint32_t bytes) {
    asm volatile("mbarrier.arrive.expect_tx.shared::cta.b64 _, [%0], %1;" ::"r"(bar), "r"(bytes) : "memory");
}
__device__ __forceinline__ void mbar_arrive(uint32_t bar) {
    asm volatile("mbarrier.arrive.shared::cta.b64 _, [%0];" ::"r"(bar) : "memory");
}
__device__ __forceinline__ bool mbar_try_wait(uint32_t bar, uint32_t parity) {
    uint32_t ok;
    asm volatile(
        "{\n .reg .pred p;\n mbarrier.try_wait.parity.shared::cta.b64 p, [%1], %2;\n selp.u32 %0, 1, 0, p;\n}"
        : "=r"(ok) : "r"(bar), "r"(parity) : "memory");
    return ok != 0;
}
__device__ __forceinline__ void mbar_wait(uint32_t bar) {
    for (int i = 0; i < (1 << 24); ++i)
        if (mbar_try_wait(bar, 0)) break;
}
__device__ __forceinline__ void mbar_wait_n(uint32_t bar, int n) {
    for (int i = 0; i < n; ++i) mbar_wait(bar + 8 * i);
}
#define TAIL_WAIT(bar, n) mbar_wait_n(bar, n)
__device__ __forceinline__ void tma_load_2d(uint32_t dst, const CUtensorMap* tm, int c0, int c1, uint32_t bar) {
    asm volatile(
        "cp.async.bulk.tensor.2d.shared::cluster.global.mbarrier::complete_tx::bytes [%0], [%1, {%3, %4}], [%2];"
        ::"r"(dst), "l"(tm), "r"(bar), "r"(c0), "r"(c1) : "memory");
}
__device__ __forceinline__ void bulk_load(uint32_t dst, const void* src, uint32_t bytes, uint32_t bar) {
    asm volatile(
        "cp.async.bulk.shared::cluster.global.mbarrier::complete_tx::bytes [%0], [%1], %2, [%3];"
        ::"r"(dst), "l"(src), "r"(bytes), "r"(bar) : "memory");
}
__device__ __forceinline__ void fence_proxy_async() { asm volatile("fence.proxy.async.shared::cta;" ::: "memory"); }
__device__ __forceinline__ void named_bar_sync(int id, int n) { asm volatile("bar.sync %0, %1;" ::"r"(id), "r"(n) : "memory"); }
#define CSYNC() named_bar_sync(1, NT)

__device__ __forceinline__ uint4 ldr4(const void* p) {
    uint4 v;
    asm volatile("ld.relaxed.gpu.global.v4.u32 {%0,%1,%2,%3}, [%4];"
                 : "=r"(v.x), "=r"(v.y), "=r"(v.z), "=r"(v.w) : "l"(p) : "memory");
    return v;
}
__device__ __forceinline__ uint2 ldr2(const void* p) {
    uint2 v;
    asm volatile("ld.relaxed.gpu.global.v2.u32 {%0,%1}, [%2];" : "=r"(v.x), "=r"(v.y) : "l"(p) : "memory");
    return v;
}
__device__ __forceinline__ uint32_t ldr1(const void* p) {
    uint32_t v;
    asm volatile("ld.relaxed.gpu.global.u32 %0, [%1];" : "=r"(v) : "l"(p) : "memory");
    return v;
}
__device__ __forceinline__ void str4(void* p, uint4 v) {
    asm volatile("st.relaxed.gpu.global.v4.u32 [%0], {%1,%2,%3,%4};" ::"l"(p), "r"(v.x), "r"(v.y), "r"(v.z), "r"(v.w) : "memory");
}
__device__ __forceinline__ void str1(void* p, uint32_t v) {
    asm volatile("st.relaxed.gpu.global.u32 [%0], %1;" ::"l"(p), "r"(v) : "memory");
}
__device__ __forceinline__ uint32_t nzw(uint32_t w) { return w ? w : 0x80000000u; }
__device__ __forceinline__ uint32_t nzf(float f) { return nzw(__float_as_uint(f)); }
__device__ __forceinline__ uint4 nz4(uint4 v) { return make_uint4(nzw(v.x), nzw(v.y), nzw(v.z), nzw(v.w)); }
__device__ __forceinline__ bool all_nz(const uint4& v) { return v.x && v.y && v.z && v.w; }
__device__ __forceinline__ uint32_t tagf(float f, uint32_t tg) { return (__float_as_uint(f) & ~3u) | tg; }
__device__ __forceinline__ bool tag_ok(uint32_t w, uint32_t tg) { return (w & 3u) == tg; }
__device__ __forceinline__ bool tag_ok4(const uint4& v, uint32_t tg) {
    return (((v.x ^ tg) | (v.y ^ tg) | (v.z ^ tg) | (v.w ^ tg)) & 3u) == 0u;
}
__device__ __forceinline__ uint32_t lda1(const void* p) {
    uint32_t v;
    asm volatile("ld.acquire.gpu.global.u32 %0, [%1];" : "=r"(v) : "l"(p) : "memory");
    return v;
}
__device__ __forceinline__ void fence_gpu() { asm volatile("fence.acq_rel.gpu;" ::: "memory"); }

__device__ __forceinline__ uint4 lds128(const void* p) { return *reinterpret_cast<const uint4*>(p); }
__device__ __forceinline__ uint2 lds64(const void* p) { return *reinterpret_cast<const uint2*>(p); }
__device__ __forceinline__ float bf_lo(uint32_t w) { return __uint_as_float(w << 16); }
__device__ __forceinline__ float bf_hi(uint32_t w) { return __uint_as_float(w & 0xffff0000u); }
__device__ __forceinline__ uint32_t pack_bf16(float lo, float hi) {
    __nv_bfloat162 v = __floats2bfloat162_rn(lo, hi);
    return *reinterpret_cast<uint32_t*>(&v);
}

__device__ __forceinline__ void ldmatrix_x4(uint32_t (&r)[4], uint32_t addr) {
    asm volatile("ldmatrix.sync.aligned.m8n8.x4.shared.b16 {%0,%1,%2,%3}, [%4];"
                 : "=r"(r[0]), "=r"(r[1]), "=r"(r[2]), "=r"(r[3]) : "r"(addr) : "memory");
}
__device__ __forceinline__ void ldmatrix_x4_trans(uint32_t (&r)[4], uint32_t addr) {
    asm volatile("ldmatrix.sync.aligned.m8n8.x4.trans.shared.b16 {%0,%1,%2,%3}, [%4];"
                 : "=r"(r[0]), "=r"(r[1]), "=r"(r[2]), "=r"(r[3]) : "r"(addr) : "memory");
}
__device__ __forceinline__ void mma_bf16(float (&d)[4], const uint32_t (&a)[4], uint32_t b0, uint32_t b1) {
    asm volatile(
        "mma.sync.aligned.m16n8k16.row.col.f32.bf16.bf16.f32 {%0,%1,%2,%3}, {%4,%5,%6,%7}, {%8,%9}, {%0,%1,%2,%3};"
        : "+f"(d[0]), "+f"(d[1]), "+f"(d[2]), "+f"(d[3])
        : "r"(a[0]), "r"(a[1]), "r"(a[2]), "r"(a[3]), "r"(b0), "r"(b1));
}

__device__ __forceinline__ uint64_t make_desc_sw128(uint32_t saddr) {
    uint64_t d = 0;
    d |= (uint64_t)((saddr & 0x3FFFF) >> 4);
    d |= (uint64_t)1 << 16;
    d |= (uint64_t)(1024 >> 4) << 32;
    d |= (uint64_t)1 << 62;
    return d;
}
__device__ __forceinline__ void wgmma_fence() { asm volatile("wgmma.fence.sync.aligned;" ::: "memory"); }
__device__ __forceinline__ void wgmma_commit() { asm volatile("wgmma.commit_group.sync.aligned;" ::: "memory"); }
__device__ __forceinline__ void wgmma_wait0() { asm volatile("wgmma.wait_group.sync.aligned 0;" ::: "memory"); }
__device__ __forceinline__ void wgmma_m64n32k16(float (&d)[16], uint64_t da, uint64_t db, int scale_d) {
    asm volatile(
        "{\n .reg .pred p;\n setp.ne.b32 p, %18, 0;\n"
        "wgmma.mma_async.sync.aligned.m64n32k16.f32.bf16.bf16 "
        "{%0,%1,%2,%3,%4,%5,%6,%7,%8,%9,%10,%11,%12,%13,%14,%15}, %16, %17, p, 1, 1, 0, 0;\n}"
        : "+f"(d[0]), "+f"(d[1]), "+f"(d[2]), "+f"(d[3]), "+f"(d[4]), "+f"(d[5]), "+f"(d[6]), "+f"(d[7]),
          "+f"(d[8]), "+f"(d[9]), "+f"(d[10]), "+f"(d[11]), "+f"(d[12]), "+f"(d[13]), "+f"(d[14]), "+f"(d[15])
        : "l"(da), "l"(db), "r"(scale_d));
}

#define TSTAMP(i) do { } while (0)

__device__ __forceinline__ void cnt_arrive(uint32_t* cnt) {
    asm volatile("red.release.gpu.global.add.u32 [%0], 1;" ::"l"(cnt) : "memory");
}
__device__ __forceinline__ void cnt_wait(const uint32_t* cnt, uint32_t target) {
    for (int it = 0; it < SPIN_MAX; ++it)
        if ((int32_t)(ldr1(cnt) - target) >= 0) break;
    fence_gpu();
}

__device__ __forceinline__ float warp_sum(float v) {
#pragma unroll
    for (int o = 16; o; o >>= 1) v += __shfl_xor_sync(0xffffffffu, v, o);
    return v;
}
__device__ __forceinline__ float warp_max(float v) {
#pragma unroll
    for (int o = 16; o; o >>= 1) v = fmaxf(v, __shfl_xor_sync(0xffffffffu, v, o));
    return v;
}

__device__ __forceinline__ void ln_stats(const float* vec, float& mean, float& rstd) {
    const int lane = threadIdx.x & 31;
    float v[20];
    float s = 0.f;
#pragma unroll
    for (int i = 0; i < 20; ++i) { v[i] = vec[lane + 32 * i]; s += v[i]; }
    mean = warp_sum(s) * (1.0f / M_);
    float s2 = 0.f;
#pragma unroll
    for (int i = 0; i < 20; ++i) { const float d = v[i] - mean; s2 += d * d; }
    const float var = warp_sum(s2) * (1.0f / M_);
    rstd = 1.0f / sqrtf(var + 1e-5f);
}

template <int R>
__device__ __forceinline__ float vecmat128(const float* vec, float sub, float mul, const uint8_t* W, float* red) {
    const int t = threadIdx.x, lane = t & 31, warp = t >> 5;
    const int cg = t & 15, rg = t >> 4;
    float acc[8];
#pragma unroll
    for (int k = 0; k < 8; ++k) acc[k] = 0.f;
#pragma unroll
    for (int r = 0; r < R / 16; ++r) {
        const int row = rg + 16 * r;
        const uint4 w = lds128(W + row * 256 + cg * 16);
        const float v = (vec[row] - sub) * mul;
        acc[0] += v * bf_lo(w.x); acc[1] += v * bf_hi(w.x);
        acc[2] += v * bf_lo(w.y); acc[3] += v * bf_hi(w.y);
        acc[4] += v * bf_lo(w.z); acc[5] += v * bf_hi(w.z);
        acc[6] += v * bf_lo(w.w); acc[7] += v * bf_hi(w.w);
    }
#pragma unroll
    for (int k = 0; k < 8; ++k) acc[k] += __shfl_xor_sync(0xffffffffu, acc[k], 16);
    if (lane < 16) {
        float4* dst = reinterpret_cast<float4*>(red + warp * 128 + cg * 8);
        dst[0] = make_float4(acc[0], acc[1], acc[2], acc[3]);
        dst[1] = make_float4(acc[4], acc[5], acc[6], acc[7]);
    }
    CSYNC();
    float r = 0.f;
    if (t < 128) {
#pragma unroll
        for (int w = 0; w < 8; ++w) r += red[w * 128 + t];
    }
    return r;
}

template <int R>
__device__ __forceinline__ float4 vecmat640(const float* vec, const uint8_t* W) {
    const int t = threadIdx.x;
    float4 a = make_float4(0.f, 0.f, 0.f, 0.f);
#pragma unroll 8
    for (int r = 0; r < R; ++r) {
        const uint2 w = lds64(W + r * 1280 + 8 * t);
        const float v = vec[r];
        a.x += v * bf_lo(w.x); a.y += v * bf_hi(w.x);
        a.z += v * bf_lo(w.y); a.w += v * bf_hi(w.y);
    }
    return a;
}

__device__ __forceinline__ float gelu_tanh(float g) {
    const float k0 = 0.7978845608028654f, k1 = 0.044715f;
    return 0.5f * g * (1.0f + tanhf(k0 * (g + k1 * g * g * g)));
}

__global__ void __launch_bounds__(NTHREADS, 1)
fused_decode_kernel(const __grid_constant__ CUtensorMap tm_wq, const __grid_constant__ CUtensorMap tm_wuk,
                    const __grid_constant__ CUtensorMap tm_ckv, const __grid_constant__ CUtensorMap tm_wuv,
                    const __grid_constant__ CUtensorMap tm_wg, const __grid_constant__ CUtensorMap tm_wu,
                    const __nv_bfloat16* __restrict__ x, const __nv_bfloat16* __restrict__ w_o,
                    const __nv_bfloat16* __restrict__ w_down, __nv_bfloat16* __restrict__ out,
                    const __nv_bfloat16* __restrict__ w_gate, const __nv_bfloat16* __restrict__ w_up) {
    extern __shared__ uint8_t smem_raw[];
    uint8_t* smem = reinterpret_cast<uint8_t*>((reinterpret_cast<uintptr_t>(smem_raw) + 1023) & ~(uintptr_t)1023);
    const int t = threadIdx.x, lane = t & 31, warp = t >> 5;
    const int b = blockIdx.x, h = b >> 2, j = b & 3;
    const uint32_t sbase = smem_u32(smem);
    const uint32_t bar0 = sbase + OFF_BAR;

    TSTAMP(0);
    if (t == 0) {
#pragma unroll
        for (int i = 0; i < NBARS; ++i) mbar_init(bar0 + 8 * i, i == BAR_GU ? 32 : 1);
        asm volatile("fence.mbarrier_init.release.cluster;" ::: "memory");
        fence_proxy_async();
    }
    __syncthreads();

    if (warp == 8) {
        if (lane == 0) {
            for (int i = 0; i < BAR_GU; ++i) {
                if (i >= INFLIGHT) mbar_wait(bar0 + 8 * (i - INFLIGHT));
                const uint32_t bar = bar0 + 8 * i;
                if (i < BAR_WUK) {
                    mbar_expect_tx(bar, 10240);
                    tma_load_2d(sbase + OFF_WQ + i * 10240, &tm_wq, h * 128, 160 * j + 40 * i, bar);
                } else if (i < BAR_CKV) {
                    const int k = i - BAR_WUK;
                    mbar_expect_tx(bar, 8192);
                    tma_load_2d(sbase + OFF_WUK + k * 8192, &tm_wuk, h * 128, 128 * j + 32 * k, bar);
                } else if (i < BAR_WUV) {
                    const int k = i - BAR_CKV;
                    mbar_expect_tx(bar, 8192);
                    tma_load_2d(sbase + OFF_CKV + k * 8192, &tm_ckv, 64 * k, 64 * b, bar);
                } else if (i < BAR_WO) {
                    const int k = i - BAR_WUV;
                    if (k == 0) mbar_wait(bar0 + 8 * BAR_GATE1);
                    mbar_expect_tx(bar, 8192);
                    tma_load_2d(sbase + OFF_WUV + k * 8192, &tm_wuv, h * 128, 128 * j + 32 * k, bar);
                } else {
                    const int k = i - BAR_WO;
                    mbar_expect_tx(bar, 10240);
                    bulk_load(sbase + OFF_WO + k * 10240, w_o + (size_t)(h * 128 + 32 * j + 8 * k) * M_, 10240, bar);
                }
            }
        }
        __syncwarp();
        if (b < NFFN) {
            mbar_wait(bar0 + 8 * BAR_FREE_WQ);
            mbar_wait(bar0 + 8 * BAR_GATE2);
#pragma unroll 4
            for (int it = 0; it < 40; ++it) {
                const int row = it * 32 + lane;
                const __nv_bfloat16* src = (row < 640 ? w_gate + (size_t)row * 1728 : w_up + (size_t)(row - 640) * 1728) + 16 * b;
                const uint32_t dst = sbase + OFF_WQ + row * 32;
                asm volatile("cp.async.cg.shared.global [%0], [%1], 16;" ::"r"(dst), "l"(src) : "memory");
                asm volatile("cp.async.cg.shared.global [%0], [%1], 16;" ::"r"(dst + 16), "l"(src + 8) : "memory");
            }
            asm volatile("cp.async.mbarrier.arrive.noinc.shared::cta.b64 [%0];" ::"r"(bar0 + 8 * BAR_GU) : "memory");
            if (lane == 0) {
                mbar_wait(bar0 + 8 * BAR_FREE_CKV);
#pragma unroll
                for (int k = 0; k < 2; ++k) {
                    mbar_expect_tx(bar0 + 8 * (BAR_DN + k), 10240);
                    bulk_load(sbase + OFF_CKV + k * 10240, w_down + (size_t)(16 * b + 8 * k) * M_, 10240, bar0 + 8 * (BAR_DN + k));
                }
            }
        }
        return;
    }

    float* red   = reinterpret_cast<float*>(smem + OFF_RED);
    float* vec_s = reinterpret_cast<float*>(smem + OFF_VEC);
    float* sm    = reinterpret_cast<float*>(smem + OFF_SM);
    float* sm_q     = sm;
    float* sm_scale = sm + 128;
    float* sm_ctxc  = sm + 256;
    float* sm_ctx   = sm + 384;
    float* sm_tmp   = sm + 416;
    float* sm_wmax  = sm + 544;
    float* sm_wsum  = sm + 672;
    float* sm_act   = sm + 800;
    float* sm_red2  = sm + 816;
    float* sm_bred  = sm + 944;
    uint32_t* sm_qa = reinterpret_cast<uint32_t*>(sm + 960);

    const uint32_t epoch = ldr1(&g_epoch) + 1u;
    const uint32_t tg = epoch & 3u;

    if (t < 80) {
        const uint4 w = *reinterpret_cast<const uint4*>(x + 8 * t);
        float4* d = reinterpret_cast<float4*>(vec_s + 8 * t);
        d[0] = make_float4(bf_lo(w.x), bf_hi(w.x), bf_lo(w.y), bf_hi(w.y));
        d[1] = make_float4(bf_lo(w.z), bf_hi(w.z), bf_lo(w.w), bf_hi(w.w));
    }
    CSYNC();
    float mean1, rstd1;
    ln_stats(vec_s, mean1, rstd1);
    TSTAMP(1);

    mbar_wait_n(bar0 + 8 * BAR_WQ, 4);
    TSTAMP(2);
    {
        const float qp = vecmat128<160>(vec_s + 160 * j, mean1, rstd1, smem + OFF_WQ, red);
        if (t < 128) str1(&g_x0[(h * 4 + j) * 128 + t], tagf(qp, tg));
        if (t == 0) mbar_arrive(bar0 + 8 * BAR_FREE_WQ);
    }
    if (t < 128) {
        float s = 0.f;
#pragma unroll
        for (int jj = 0; jj < 4; ++jj) {
            uint32_t w = 0;
            for (int it = 0; it < SPIN_MAX; ++it) {
                w = ldr1(&g_x0[(h * 4 + jj) * 128 + t]);
                if (tag_ok(w, tg)) break;
            }
            s += __uint_as_float(w);
        }
        sm_q[t] = s;
    }
    CSYNC();
    TSTAMP(3);

    mbar_wait_n(bar0 + 8 * BAR_WUK, 4);
    TSTAMP(4);
    {
        const int cg = t & 15, rg = t >> 4;
        float qv[8];
#pragma unroll
        for (int k = 0; k < 8; ++k) qv[k] = sm_q[8 * cg + k];
        float acc[8];
#pragma unroll
        for (int i = 0; i < 8; ++i) {
            const int row = 32 * (i >> 1) + 2 * rg + (i & 1);
            const uint4 w = lds128(smem + OFF_WUK + row * 256 + cg * 16);
            acc[i] = qv[0] * bf_lo(w.x) + qv[1] * bf_hi(w.x) + qv[2] * bf_lo(w.y) + qv[3] * bf_hi(w.y) +
                     qv[4] * bf_lo(w.z) + qv[5] * bf_hi(w.z) + qv[6] * bf_lo(w.w) + qv[7] * bf_hi(w.w);
        }
#pragma unroll
        for (int o = 1; o <= 8; o <<= 1)
#pragma unroll
            for (int i = 0; i < 8; ++i) acc[i] += __shfl_xor_sync(0xffffffffu, acc[i], o);
        if (cg == 0) {
            const float sc = 0.08838834764831845f * 1.4426950408889634f;
#pragma unroll
            for (int k = 0; k < 4; ++k) sm_qa[16 * k + rg] = pack_bf16(acc[2 * k] * sc, acc[2 * k + 1] * sc);
        }
    }
    CSYNC();
    if (warp == 0) {
        if (t < 16) str4(&g_x1[(h * DC_ + 128 * j) / 2 + 4 * t], *reinterpret_cast<const uint4*>(sm_qa + 4 * t));
        __syncwarp();
        if (t == 0) cnt_arrive(&g_cnt[0]);
    }
    TSTAMP(5);

    {
        if (t == 0) cnt_wait(&g_cnt[0], epoch * NCTA);
        CSYNC();
        const uint8_t* src = reinterpret_cast<const uint8_t*>(g_x1) + warp * 4096 + lane * 16;
        uint4 v[8];
#pragma unroll
        for (int i = 0; i < 8; ++i) v[i] = ldr4(src + 512 * i);
#pragma unroll
        for (int i = 0; i < 8; ++i) {
            const int q = (warp * 8 + i) * 32 + lane;
            const int hq = q >> 6, c8 = q & 63;
            *reinterpret_cast<uint4*>(smem + OFF_WUK + (c8 >> 3) * 4096 + hq * 128 + (((c8 & 7) ^ (hq & 7)) << 4)) = v[i];
        }
        fence_proxy_async();
    }
    CSYNC();
    if (t == 0) mbar_arrive(bar0 + 8 * BAR_GATE1);
    TSTAMP(6);

    mbar_wait_n(bar0 + 8 * BAR_CKV, 8);
    TSTAMP(7);
    if (warp < 4) {
        float s[16];
#pragma unroll
        for (int i = 0; i < 16; ++i) s[i] = 0.f;
        wgmma_fence();
#pragma unroll
        for (int kb = 0; kb < 8; ++kb)
#pragma unroll
            for (int ks = 0; ks < 4; ++ks)
                wgmma_m64n32k16(s, make_desc_sw128(sbase + OFF_CKV + kb * 8192 + ks * 32),
                                make_desc_sw128(sbase + OFF_WUK + kb * 4096 + ks * 32), (kb | ks) != 0);
        wgmma_commit();
        wgmma_wait0();
        float mx[8];
#pragma unroll
        for (int i = 0; i < 4; ++i)
#pragma unroll
            for (int c = 0; c < 2; ++c) mx[2 * i + c] = fmaxf(s[4 * i + c], s[4 * i + 2 + c]);
#pragma unroll
        for (int o = 4; o <= 16; o <<= 1)
#pragma unroll
            for (int k = 0; k < 8; ++k) mx[k] = fmaxf(mx[k], __shfl_xor_sync(0xffffffffu, mx[k], o));
        if (lane < 4) {
#pragma unroll
            for (int i = 0; i < 4; ++i)
#pragma unroll
                for (int c = 0; c < 2; ++c) sm_wmax[warp * 32 + 8 * i + 2 * lane + c] = mx[2 * i + c];
        }
        named_bar_sync(2, 128);
#pragma unroll
        for (int i = 0; i < 4; ++i)
#pragma unroll
            for (int c = 0; c < 2; ++c) {
                const int head = 8 * i + 2 * (lane & 3) + c;
                mx[2 * i + c] = fmaxf(fmaxf(sm_wmax[head], sm_wmax[32 + head]), fmaxf(sm_wmax[64 + head], sm_wmax[96 + head]));
            }
        float sum[8];
#pragma unroll
        for (int i = 0; i < 4; ++i)
#pragma unroll
            for (int e = 0; e < 4; ++e) s[4 * i + e] = exp2f(s[4 * i + e] - mx[2 * i + (e & 1)]);
#pragma unroll
        for (int i = 0; i < 4; ++i)
#pragma unroll
            for (int c = 0; c < 2; ++c) sum[2 * i + c] = s[4 * i + c] + s[4 * i + 2 + c];
#pragma unroll
        for (int o = 4; o <= 16; o <<= 1)
#pragma unroll
            for (int k = 0; k < 8; ++k) sum[k] += __shfl_xor_sync(0xffffffffu, sum[k], o);
        if (lane < 4) {
#pragma unroll
            for (int i = 0; i < 4; ++i)
#pragma unroll
                for (int c = 0; c < 2; ++c) sm_wsum[warp * 32 + 8 * i + 2 * lane + c] = sum[2 * i + c];
        }
        __nv_bfloat16* Ps = reinterpret_cast<__nv_bfloat16*>(smem + OFF_P);
#pragma unroll
        for (int i = 0; i < 4; ++i)
#pragma unroll
            for (int e = 0; e < 4; ++e) {
                const int head = 8 * i + 2 * (lane & 3) + (e & 1);
                const int key = 16 * warp + (lane >> 2) + 8 * (e >> 1);
                Ps[head * 72 + key] = __float2bfloat16_rn(s[4 * i + e]);
            }
    }
    CSYNC();
    TSTAMP(8);
    {
        uint32_t a[2][4][4];
#pragma unroll
        for (int mt = 0; mt < 2; ++mt)
#pragma unroll
            for (int ks = 0; ks < 4; ++ks)
                ldmatrix_x4(a[mt][ks], sbase + OFF_P + (16 * mt + (lane & 15)) * 144 + (16 * ks + (lane >> 4) * 8) * 2);
        float o[2][8][4];
#pragma unroll
        for (int mt = 0; mt < 2; ++mt)
#pragma unroll
            for (int nt = 0; nt < 8; ++nt)
#pragma unroll
                for (int e = 0; e < 4; ++e) o[mt][nt][e] = 0.f;
        const uint32_t blk = sbase + OFF_CKV + warp * 8192;
#pragma unroll
        for (int ks = 0; ks < 4; ++ks)
#pragma unroll
            for (int np = 0; np < 4; ++np) {
                const int m = lane >> 3;
                const int r = 16 * ks + (lane & 7) + 8 * (m & 1);
                const int ch = 2 * np + (m >> 1);
                uint32_t bf[4];
                ldmatrix_x4_trans(bf, blk + r * 128 + ((ch ^ (r & 7)) << 4));
#pragma unroll
                for (int mt = 0; mt < 2; ++mt) {
                    mma_bf16(o[mt][2 * np], a[mt][ks], bf[0], bf[1]);
                    mma_bf16(o[mt][2 * np + 1], a[mt][ks], bf[2], bf[3]);
                }
            }
        const int g = lane >> 2, tq = lane & 3;
#pragma unroll
        for (int mt = 0; mt < 2; ++mt)
#pragma unroll
            for (int hf = 0; hf < 2; ++hf) {
                const int head = 16 * mt + g + 8 * hf;
#pragma unroll
                for (int nt = 0; nt < 8; ++nt) {
                    const int ch = 8 * warp + nt;
                    *reinterpret_cast<uint32_t*>(smem + OFF_WUK + head * 1024 + ((ch ^ (head & 7)) << 4) + tq * 4) =
                        pack_bf16(o[mt][nt][2 * hf], o[mt][nt][2 * hf + 1]);
                }
            }
    }
    CSYNC();
    if (t == 0) mbar_arrive(bar0 + 8 * BAR_FREE_CKV);
    TSTAMP(9);
    {
#pragma unroll
        for (int i = 0; i < 8; ++i) {
            const int q = t + 256 * i;
            const int head = q >> 6, ch = q & 63;
            const uint4 v = lds128(smem + OFF_WUK + head * 1024 + ((ch ^ (head & 7)) << 4));
            str4(g_x2 + (size_t)((head * 4 + (ch >> 4)) * 128 + b) * X2_ROW + (ch & 15) * 16, v);
        }
        if (t < 128) {
            const int head = t & 31, jj = t >> 5;
            const float m = fmaxf(fmaxf(sm_wmax[head], sm_wmax[32 + head]), fmaxf(sm_wmax[64 + head], sm_wmax[96 + head]));
            const float l = sm_wsum[head] + sm_wsum[32 + head] + sm_wsum[64 + head] + sm_wsum[96 + head];
            uint8_t* dst = g_x2 + (size_t)((head * 4 + jj) * 128 + b) * X2_ROW + 256;
            str4(dst, make_uint4(__float_as_uint(m), __float_as_uint(l), 0u, 0u));
            str4(dst + 16, make_uint4(0u, 0u, 0u, 0u));
        }
        CSYNC();
        if (t == 0) cnt_arrive(&g_cnt[32]);
    }
    TSTAMP(10);

    {
        uint8_t* xbase = g_x2 + (size_t)((h * 4 + j) * 128) * X2_ROW;
        if (t == 0) cnt_wait(&g_cnt[32], epoch * NCTA);
        CSYNC();
        TSTAMP(11);
        const int cg = t & 15, rg = t >> 4;
        uint4 v[8];
        uint2 st[8];
#pragma unroll
        for (int i = 0; i < 8; ++i) v[i] = ldr4(xbase + (rg + 16 * i) * X2_ROW + cg * 16);
#pragma unroll
        for (int i = 0; i < 8; ++i) st[i] = ldr2(xbase + (rg + 16 * i) * X2_ROW + 256);
        float ml = __uint_as_float(st[0].x);
#pragma unroll
        for (int i = 1; i < 8; ++i) ml = fmaxf(ml, __uint_as_float(st[i].x));
        float acc[8], ll = 0.f;
#pragma unroll
        for (int k = 0; k < 8; ++k) acc[k] = 0.f;
#pragma unroll
        for (int i = 0; i < 8; ++i) {
            const float f = exp2f(__uint_as_float(st[i].x) - ml);
            ll += f * __uint_as_float(st[i].y);
            acc[0] += f * bf_lo(v[i].x); acc[1] += f * bf_hi(v[i].x);
            acc[2] += f * bf_lo(v[i].y); acc[3] += f * bf_hi(v[i].y);
            acc[4] += f * bf_lo(v[i].z); acc[5] += f * bf_hi(v[i].z);
            acc[6] += f * bf_lo(v[i].w); acc[7] += f * bf_hi(v[i].w);
        }
        {
            const float mo = __shfl_xor_sync(0xffffffffu, ml, 16);
            const float lo = __shfl_xor_sync(0xffffffffu, ll, 16);
            const float mm = fmaxf(ml, mo);
            const float fa = exp2f(ml - mm), fb = exp2f(mo - mm);
#pragma unroll
            for (int k = 0; k < 8; ++k) acc[k] = fa * acc[k] + fb * __shfl_xor_sync(0xffffffffu, acc[k], 16);
            ll = fa * ll + fb * lo;
            ml = mm;
        }
        if (lane < 16) {
            float4* dst = reinterpret_cast<float4*>(red + warp * 128 + cg * 8);
            dst[0] = make_float4(acc[0], acc[1], acc[2], acc[3]);
            dst[1] = make_float4(acc[4], acc[5], acc[6], acc[7]);
            if (lane == 0) { sm_bred[warp] = ml; sm_bred[8 + warp] = ll; }
        }
        CSYNC();
        if (t < 128) {
            float M = sm_bred[0];
#pragma unroll
            for (int w = 1; w < 8; ++w) M = fmaxf(M, sm_bred[w]);
            float r = 0.f, L = 0.f;
#pragma unroll
            for (int w = 0; w < 8; ++w) {
                const float f = exp2f(sm_bred[w] - M);
                r += f * red[w * 128 + t];
                L += f * sm_bred[8 + w];
            }
            sm_ctxc[t] = r / L;
        }
        if (t == 0) mbar_arrive(bar0 + 8 * BAR_GATE2);
        CSYNC();
        TSTAMP(12);
        TAIL_WAIT(bar0 + 8 * BAR_WUV, 4);
        const float cp = vecmat128<128>(sm_ctxc, 0.f, 1.f, smem + OFF_WUV, red);
        if (t < 128) str1(&g_x2b[(h * 4 + j) * 128 + t], tagf(cp, tg));
        TSTAMP(13);
    }

    if (t < 128) {
        const int jj = t >> 5, dd = t & 31;
        float* p = &g_x2b[(h * 4 + jj) * 128 + 32 * j + dd];
        uint32_t w = 0;
        for (int it = 0; it < SPIN_MAX; ++it) {
            w = ldr1(p);
            if (tag_ok(w, tg)) break;
        }
        sm_tmp[t] = __uint_as_float(w);
    }
    CSYNC();
    if (t < 32) sm_ctx[t] = (sm_tmp[t] + sm_tmp[32 + t]) + (sm_tmp[64 + t] + sm_tmp[96 + t]);
    CSYNC();
    TSTAMP(14);
    TAIL_WAIT(bar0 + 8 * BAR_WO, 4);
    if (t < 160) {
        const float4 a = vecmat640<32>(sm_ctx, smem + OFF_WO);
        const int cb = t >> 1, e = (t & 1) * 4;
        str4(&g_x3[(cb * 128 + b) * 8 + e], make_uint4(__float_as_uint(a.x), __float_as_uint(a.y), __float_as_uint(a.z), __float_as_uint(a.w)));
    }
    CSYNC();
    if (t == 0) cnt_arrive(&g_cnt[64]);
    TSTAMP(15);

    float h_own = 0.f;
    if (b < NRS) {
        float* p = &g_x3[(size_t)(b * 128) * 8 + t * 4];
        if (t == 0) cnt_wait(&g_cnt[64], epoch * NCTA);
        CSYNC();
        const uint4 w = ldr4(p);
        float v0 = __uint_as_float(w.x), v1 = __uint_as_float(w.y), v2 = __uint_as_float(w.z), v3 = __uint_as_float(w.w);
#pragma unroll
        for (int o = 2; o <= 16; o <<= 1) {
            v0 += __shfl_xor_sync(0xffffffffu, v0, o); v1 += __shfl_xor_sync(0xffffffffu, v1, o);
            v2 += __shfl_xor_sync(0xffffffffu, v2, o); v3 += __shfl_xor_sync(0xffffffffu, v3, o);
        }
        if (lane < 2) {
            float4* dst = reinterpret_cast<float4*>(sm_red2 + warp * 8 + lane * 4);
            *dst = make_float4(v0, v1, v2, v3);
        }
        CSYNC();
        if (t < 8) {
            float a = 0.f;
#pragma unroll
            for (int w8 = 0; w8 < 8; ++w8) a += sm_red2[w8 * 8 + t];
            h_own = __bfloat162float(x[8 * b + t]) + a;
            str1(&g_x3b[8 * b + t], tagf(h_own, tg));
        }
    }
    TSTAMP(16);

    if (b < NFFN) {
        if (t < 160) {
            const float* p = &g_x3b[4 * t];
            uint4 w;
            for (int it = 0; it < SPIN_MAX; ++it) {
                w = ldr4(p);
                if (tag_ok4(w, tg)) break;
            }
            *reinterpret_cast<float4*>(vec_s + 4 * t) =
                make_float4(__uint_as_float(w.x), __uint_as_float(w.y), __uint_as_float(w.z), __uint_as_float(w.w));
        }
        CSYNC();
        TSTAMP(17);
        float mean2, rstd2;
        ln_stats(vec_s, mean2, rstd2);

        TAIL_WAIT(bar0 + 8 * BAR_GU, 1);
        TSTAMP(18);
        {
            const int mat = t >> 7, cc = t & 1, rg = (t & 127) >> 1;
            const uint8_t* W = smem + OFF_WQ + mat * 20480;
            float acc[8];
#pragma unroll
            for (int k = 0; k < 8; ++k) acc[k] = 0.f;
#pragma unroll
            for (int i = 0; i < 10; ++i) {
                const int row = rg + 64 * i;
                const uint4 w = lds128(W + row * 32 + cc * 16);
                const float v = (vec_s[row] - mean2) * rstd2;
                acc[0] += v * bf_lo(w.x); acc[1] += v * bf_hi(w.x);
                acc[2] += v * bf_lo(w.y); acc[3] += v * bf_hi(w.y);
                acc[4] += v * bf_lo(w.z); acc[5] += v * bf_hi(w.z);
                acc[6] += v * bf_lo(w.w); acc[7] += v * bf_hi(w.w);
            }
#pragma unroll
            for (int o = 2; o <= 16; o <<= 1)
#pragma unroll
                for (int k = 0; k < 8; ++k) acc[k] += __shfl_xor_sync(0xffffffffu, acc[k], o);
            if (lane < 2) {
                float4* dst = reinterpret_cast<float4*>(sm_red2 + warp * 16 + lane * 8);
                dst[0] = make_float4(acc[0], acc[1], acc[2], acc[3]);
                dst[1] = make_float4(acc[4], acc[5], acc[6], acc[7]);
            }
        }
        CSYNC();
        if (t < 16) {
            const float gv = (sm_red2[t] + sm_red2[16 + t]) + (sm_red2[32 + t] + sm_red2[48 + t]);
            const float uv = (sm_red2[64 + t] + sm_red2[80 + t]) + (sm_red2[96 + t] + sm_red2[112 + t]);
            sm_act[t] = gelu_tanh(gv) * uv;
        }
        CSYNC();
        TAIL_WAIT(bar0 + 8 * BAR_DN, 2);
        TSTAMP(19);
        if (t < 160) {
            const float4 a = vecmat640<16>(sm_act, smem + OFF_CKV);
            const int cb = t >> 1, e = (t & 1) * 4;
            str4(&g_x4[(cb * NFFN + b) * 8 + e], make_uint4(__float_as_uint(a.x), __float_as_uint(a.y), __float_as_uint(a.z), __float_as_uint(a.w)));
        }
        CSYNC();
        if (t == 0) cnt_arrive(&g_cnt[96]);
        TSTAMP(20);
    }

    if (b < NRS) {
        float v0 = 0.f, v1 = 0.f, v2 = 0.f, v3 = 0.f;
        float* p = &g_x4[(size_t)(b * NFFN) * 8 + t * 4];
        if (t == 0) cnt_wait(&g_cnt[96], epoch * NFFN);
        CSYNC();
        if (t < 2 * NFFN) {
            const uint4 w = ldr4(p);
            v0 = __uint_as_float(w.x); v1 = __uint_as_float(w.y); v2 = __uint_as_float(w.z); v3 = __uint_as_float(w.w);
        }
#pragma unroll
        for (int o = 2; o <= 16; o <<= 1) {
            v0 += __shfl_xor_sync(0xffffffffu, v0, o); v1 += __shfl_xor_sync(0xffffffffu, v1, o);
            v2 += __shfl_xor_sync(0xffffffffu, v2, o); v3 += __shfl_xor_sync(0xffffffffu, v3, o);
        }
        CSYNC();
        if (lane < 2) {
            float4* dst = reinterpret_cast<float4*>(sm_red2 + warp * 8 + lane * 4);
            *dst = make_float4(v0, v1, v2, v3);
        }
        CSYNC();
        if (t < 8) {
            float a = 0.f;
#pragma unroll
            for (int w8 = 0; w8 < 8; ++w8) a += sm_red2[w8 * 8 + t];
            out[8 * b + t] = __float2bfloat16_rn(h_own + a);
        }
    }
    if (b == 0 && t == 0) str1(&g_epoch, epoch);
    TSTAMP(21);
}

typedef CUresult (*EncodeTiledFn)(CUtensorMap*, CUtensorMapDataType, cuuint32_t, void*, const cuuint64_t*,
                                  const cuuint64_t*, const cuuint32_t*, const cuuint32_t*, CUtensorMapInterleave,
                                  CUtensorMapSwizzle, CUtensorMapL2promotion, CUtensorMapFloatOOBfill);

bool make_map_2d(EncodeTiledFn fn, CUtensorMap* m, const void* base, uint64_t inner, uint64_t outer,
                 uint32_t box_inner, uint32_t box_outer, CUtensorMapSwizzle sw) {
    cuuint64_t gdim[2] = {inner, outer};
    cuuint64_t gstride[1] = {inner * 2};
    cuuint32_t box[2] = {box_inner, box_outer};
    cuuint32_t es[2] = {1, 1};
    return fn(m, CU_TENSOR_MAP_DATA_TYPE_BFLOAT16, 2, const_cast<void*>(base), gdim, gstride, box, es,
              CU_TENSOR_MAP_INTERLEAVE_NONE, sw, CU_TENSOR_MAP_L2_PROMOTION_L2_256B,
              CU_TENSOR_MAP_FLOAT_OOB_FILL_NONE) == CUDA_SUCCESS;
}

}

extern "C" void kernel_launch(void* const* d_in, const int* in_sizes, int n_in, void* d_out, int out_size) {
    (void)in_sizes; (void)n_in; (void)out_size;
    const __nv_bfloat16* x      = (const __nv_bfloat16*)d_in[0];
    const __nv_bfloat16* c_kv   = (const __nv_bfloat16*)d_in[1];
    const __nv_bfloat16* w_q    = (const __nv_bfloat16*)d_in[2];
    const __nv_bfloat16* w_uk   = (const __nv_bfloat16*)d_in[3];
    const __nv_bfloat16* w_uv   = (const __nv_bfloat16*)d_in[4];
    const __nv_bfloat16* w_o    = (const __nv_bfloat16*)d_in[5];
    const __nv_bfloat16* w_gate = (const __nv_bfloat16*)d_in[7];
    const __nv_bfloat16* w_up   = (const __nv_bfloat16*)d_in[8];
    const __nv_bfloat16* w_down = (const __nv_bfloat16*)d_in[9];
    __nv_bfloat16* out = (__nv_bfloat16*)d_out;

    static EncodeTiledFn fn = nullptr;
    if (!fn) {
        void* p = nullptr;
        cudaDriverEntryPointQueryResult qres;
        cudaGetDriverEntryPoint("cuTensorMapEncodeTiled", &p, cudaEnableDefault, &qres);
        fn = (EncodeTiledFn)p;
        cudaFuncSetAttribute(fused_decode_kernel, cudaFuncAttributeMaxDynamicSharedMemorySize, SMEM_ALLOC);
    }
    CUtensorMap tm_wq, tm_wuk, tm_ckv, tm_wuv, tm_wg, tm_wu;
    make_map_2d(fn, &tm_wq,  w_q,    4096, 640,  128, 40, CU_TENSOR_MAP_SWIZZLE_NONE);
    make_map_2d(fn, &tm_wuk, w_uk,   4096, 512,  128, 32, CU_TENSOR_MAP_SWIZZLE_NONE);
    make_map_2d(fn, &tm_ckv, c_kv,   512,  8192, 64,  64,  CU_TENSOR_MAP_SWIZZLE_128B);
    make_map_2d(fn, &tm_wuv, w_uv,   4096, 512,  128, 32, CU_TENSOR_MAP_SWIZZLE_NONE);
    make_map_2d(fn, &tm_wg,  w_gate, 1728, 640,  16,  160, CU_TENSOR_MAP_SWIZZLE_NONE);
    make_map_2d(fn, &tm_wu,  w_up,   1728, 640,  16,  160, CU_TENSOR_MAP_SWIZZLE_NONE);

    fused_decode_kernel<<<NCTA, NTHREADS, SMEM_ALLOC>>>(tm_wq, tm_wuk, tm_ckv, tm_wuv, tm_wg, tm_wu, x, w_o, w_down, out, w_gate, w_up);
}
```
